```python
import torch

def _softmax(x, axis=-1):
    return torch.softmax(x, dim=axis)
def _gelu(x):
    return torch.nn.functional.gelu(x, approximate="tanh")
def _silu(x):
    return torch.nn.functional.silu(x)
def _sigmoid(x):
    return torch.sigmoid(x)
def _layernorm(x, axis=-1, eps=1e-5):
    m = x.mean(dim=axis, keepdim=True)
    v = x.var(dim=axis, keepdim=True, unbiased=False)
    return (x - m) / torch.sqrt(v + eps)
def _scatter_add(tgt, idx, src, axis=0):
    return tgt.clone().index_add_(axis, idx, src)
def _segment_sum(src, seg, n):
    out = torch.zeros((n,) + src.shape[1:], dtype=src.dtype)
    return out.index_add_(0, seg, src)
def _pad(x, pw):
    flat = tuple(v for pair in reversed(pw) for v in pair)
    return torch.nn.functional.pad(x, flat)

kernel_name = 'gated_mix__grouped_kv_mqa__dense_activation_silu__prompt'

def setup_inputs():

    _w = (lambda a: (lambda t: t.to(torch.bfloat16) if t.is_floating_point() else t)(torch.as_tensor(a)))
    def _A_setup():
        B, S, D, H = 1, 2048, 1024, 32
        Dh = D // H
        return {
            "x": _w((lambda *s: torch.randn(*s, dtype=torch.bfloat16) * 0.05)(B, S, D)),
            "wq": _w((lambda *s: torch.randn(*s, dtype=torch.bfloat16) * 0.8)(D, H * Dh)),
            "wk": _w((lambda *s: torch.randn(*s, dtype=torch.bfloat16) * 0.8)(D, Dh)),
            "wv": _w((lambda *s: torch.randn(*s, dtype=torch.bfloat16) * 0.05)(D, Dh)),
            "wo": _w((lambda *s: torch.randn(*s, dtype=torch.bfloat16) * 0.05)(H * Dh, D)),
        }
    _A_in = _A_setup()

    def _B_setup():
        B, S, D, F = 1, 2048, 1024, 3584
        return {
            "x": _w((lambda *s: torch.randn(*s, dtype=torch.bfloat16) * 0.05)(B, S, D)),
            "w1": _w((lambda *s: torch.randn(*s, dtype=torch.bfloat16) * 3.2)(D, F) * (D ** -0.5)),
            "w2": _w((lambda *s: torch.randn(*s, dtype=torch.bfloat16) * 0.4)(F, D) * (F ** -0.5)),
        }
    _B_in = _B_setup()

    return {
        "A_x": _A_in["x"],
        "A_wq": _A_in["wq"],
        "A_wk": _A_in["wk"],
        "A_wv": _A_in["wv"],
        "A_wo": _A_in["wo"],
        "B_x": _B_in["x"],
        "B_w1": _B_in["w1"],
        "B_w2": _B_in["w2"],
        "gate_w": _w((lambda *s: torch.randn(*s, dtype=torch.bfloat16) * 0.05)(1024) * 16.0),
    }

def reference(A_x, A_wq, A_wk, A_wv, A_wo, B_x, B_w1, B_w2, gate_w):
    def _A_ref(x, wq, wk, wv, wo):
        B, S, D = x.shape
        H = 32
        Dh = D // H
        q = (lambda x, *d: x.permute(*d))((x @ wq).reshape(B, S, H, Dh), 0, 2, 1, 3)
        k = x @ wk
        v = x @ wv
        scores = torch.einsum("bhqd,bkd->bhqk", q, k) * (Dh ** -0.5)
        p = _softmax(scores, axis=-1)
        o = torch.einsum("bhqk,bkd->bhqd", p, v)
        return (lambda x, *d: x.permute(*d))(o, 0, 2, 1, 3).reshape(B, S, H * Dh) @ wo

    def _B_ref(x, w1, w2):
        h = torch.einsum("bsd,df->bsf", x, w1)
        h = _silu(h)
        out = torch.einsum("bsf,fd->bsd", h, w2)
        return out

    x = A_x
    g = _sigmoid((x * gate_w).sum(-1, keepdims=True))
    a = _A_ref(x, A_wq, A_wk, A_wv, A_wo)
    b = _B_ref(x, B_w1, B_w2)
    return g * a + (1 - g) * b
```

```cpp
#include <cuda_runtime.h>
#include <cuda_bf16.h>
#include <cuda.h>
#include <stdint.h>
#include <stdio.h>

namespace {

constexpr int SEQ = 2048, DM = 1024, FF = 3584;
constexpr uint32_t A1_OFF = 32768;
constexpr uint32_t B1_OFF = 98304;
constexpr uint32_t KV_OFF = 196608;
constexpr uint32_t BAR_OFF = 229376;
constexpr uint32_t ONES_OFF = BAR_OFF + 512;
constexpr uint32_t SMEM_BYTES = ONES_OFF + 1024 + 1024;
constexpr uint32_t BAR_FULL = 0, BAR_EMPTY = 32, BAR_SIG = 128;
constexpr uint32_t BAR_FULL2 = 192, BAR_EMPTY2 = 256, BAR_OWN = 320;
constexpr uint32_t DESC_HI = 0x40000040u;
constexpr uint32_t DESC_HI64 = 0x80000020u;
constexpr uint32_t LBO_A = 1u << 16;
constexpr uint32_t LBO_B1 = (32768u >> 4) << 16;
constexpr uint32_t LBO_B2 = (4096u >> 4) << 16;
constexpr uint32_t V_STEP = 1u - (1u << 16);
constexpr int N_PURE = 6;
static_assert(N_PURE % 2 == 0 && N_PURE >= 4, "key tile pairs, tile 0 activation");
constexpr int T_F2 = 32 - N_PURE;
constexpr int GS_F1 = 16, GS_F2 = 48, U_END = 72;
constexpr int U_TAIL = 3 * ((64 - T_F2) / 2);
constexpr float Q_SCALE = 0.17677669529663687f * 1.4426950408889634f;
constexpr int N_FIRST = 2;
constexpr float L_MIN = 0x1p-60f, L_MAX = 0x1p100f;
constexpr int SPIN_LIMIT = 1 << 20;

constexpr int CNT_STRIDE = 32;
constexpr int CNT_DONE = 0, CNT_KV = 1, CNT_H = 2, CNT_O = CNT_H + 32, CNT_O2 = CNT_O + 16, CNT_NUM = CNT_O2 + 16;

__device__ __align__(1024) __nv_bfloat16 g_H[SEQ * FF];
__device__ __align__(1024) __nv_bfloat16 g_O[SEQ * DM];
__device__ __align__(1024) __nv_bfloat16 g_KV[2 * SEQ * 32];
__device__ unsigned g_cnt[CNT_NUM * CNT_STRIDE];

struct Ptrs {
  const uint8_t *wk, *wv;
};
struct Maps {
  CUtensorMap x, wq, w1, w2, wo, h, o, kv, kvs;
};

__device__ __forceinline__ void mma_n208(float (&d)[104], uint32_t da, uint32_t db, int sd) {
  asm volatile("{\n.reg .pred p;\n.reg .b64 da, db;\nsetp.ne.b32 p, %107, 0;\nmov.b64 da, {%104, %106};\nmov.b64 db, {%105, %106};\n"
    "wgmma.mma_async.sync.aligned.m64n208k16.f32.bf16.bf16 "
    "{%0,%1,%2,%3,%4,%5,%6,%7,%8,%9,%10,%11,%12,%13,%14,%15,%16,%17,%18,%19,%20,%21,%22,%23,%24,%25,%26,%27,%28,%29,%30,%31,%32,%33,%34,%35,%36,%37,%38,%39,%40,%41,%42,%43,%44,%45,%46,%47,%48,%49,%50,%51,%52,%53,%54,%55,%56,%57,%58,%59,%60,%61,%62,%63,%64,%65,%66,%67,%68,%69,%70,%71,%72,%73,%74,%75,%76,%77,%78,%79,%80,%81,%82,%83,%84,%85,%86,%87,%88,%89,%90,%91,%92,%93,%94,%95,%96,%97,%98,%99,%100,%101,%102,%103}, "
    "da, db, p, 1, 1, 0, 1;\n}\n"
    : "+f"(d[0]),"+f"(d[1]),"+f"(d[2]),"+f"(d[3]),"+f"(d[4]),"+f"(d[5]),"+f"(d[6]),"+f"(d[7]),"+f"(d[8]),"+f"(d[9]),
      "+f"(d[10]),"+f"(d[11]),"+f"(d[12]),"+f"(d[13]),"+f"(d[14]),"+f"(d[15]),"+f"(d[16]),"+f"(d[17]),"+f"(d[18]),"+f"(d[19]),
      "+f"(d[20]),"+f"(d[21]),"+f"(d[22]),"+f"(d[23]),"+f"(d[24]),"+f"(d[25]),"+f"(d[26]),"+f"(d[27]),"+f"(d[28]),"+f"(d[29]),
      "+f"(d[30]),"+f"(d[31]),"+f"(d[32]),"+f"(d[33]),"+f"(d[34]),"+f"(d[35]),"+f"(d[36]),"+f"(d[37]),"+f"(d[38]),"+f"(d[39]),
      "+f"(d[40]),"+f"(d[41]),"+f"(d[42]),"+f"(d[43]),"+f"(d[44]),"+f"(d[45]),"+f"(d[46]),"+f"(d[47]),"+f"(d[48]),"+f"(d[49]),
      "+f"(d[50]),"+f"(d[51]),"+f"(d[52]),"+f"(d[53]),"+f"(d[54]),"+f"(d[55]),"+f"(d[56]),"+f"(d[57]),"+f"(d[58]),"+f"(d[59]),
      "+f"(d[60]),"+f"(d[61]),"+f"(d[62]),"+f"(d[63]),"+f"(d[64]),"+f"(d[65]),"+f"(d[66]),"+f"(d[67]),"+f"(d[68]),"+f"(d[69]),
      "+f"(d[70]),"+f"(d[71]),"+f"(d[72]),"+f"(d[73]),"+f"(d[74]),"+f"(d[75]),"+f"(d[76]),"+f"(d[77]),"+f"(d[78]),"+f"(d[79]),
      "+f"(d[80]),"+f"(d[81]),"+f"(d[82]),"+f"(d[83]),"+f"(d[84]),"+f"(d[85]),"+f"(d[86]),"+f"(d[87]),"+f"(d[88]),"+f"(d[89]),
      "+f"(d[90]),"+f"(d[91]),"+f"(d[92]),"+f"(d[93]),"+f"(d[94]),"+f"(d[95]),"+f"(d[96]),"+f"(d[97]),"+f"(d[98]),"+f"(d[99]),
      "+f"(d[100]),"+f"(d[101]),"+f"(d[102]),"+f"(d[103])
    : "r"(da),"r"(db),"r"(DESC_HI),"r"(sd));
}
__device__ __forceinline__ void mma_ss(float (&d)[104], uint32_t da, uint32_t db, int sd) {
  asm volatile("{\n.reg .pred p;\n.reg .b64 da, db;\nsetp.ne.b32 p, %99, 0;\nmov.b64 da, {%96, %98};\nmov.b64 db, {%97, %98};\n"
    "wgmma.mma_async.sync.aligned.m64n192k16.f32.bf16.bf16 "
    "{%0,%1,%2,%3,%4,%5,%6,%7,%8,%9,%10,%11,%12,%13,%14,%15,%16,%17,%18,%19,%20,%21,%22,%23,%24,%25,%26,%27,%28,%29,%30,%31,%32,%33,%34,%35,%36,%37,%38,%39,%40,%41,%42,%43,%44,%45,%46,%47,%48,%49,%50,%51,%52,%53,%54,%55,%56,%57,%58,%59,%60,%61,%62,%63,%64,%65,%66,%67,%68,%69,%70,%71,%72,%73,%74,%75,%76,%77,%78,%79,%80,%81,%82,%83,%84,%85,%86,%87,%88,%89,%90,%91,%92,%93,%94,%95}, "
    "da, db, p, 1, 1, 0, 1;\n}\n"
    : "+f"(d[0]),"+f"(d[1]),"+f"(d[2]),"+f"(d[3]),"+f"(d[4]),"+f"(d[5]),"+f"(d[6]),"+f"(d[7]),"+f"(d[8]),"+f"(d[9]),
      "+f"(d[10]),"+f"(d[11]),"+f"(d[12]),"+f"(d[13]),"+f"(d[14]),"+f"(d[15]),"+f"(d[16]),"+f"(d[17]),"+f"(d[18]),"+f"(d[19]),
      "+f"(d[20]),"+f"(d[21]),"+f"(d[22]),"+f"(d[23]),"+f"(d[24]),"+f"(d[25]),"+f"(d[26]),"+f"(d[27]),"+f"(d[28]),"+f"(d[29]),
      "+f"(d[30]),"+f"(d[31]),"+f"(d[32]),"+f"(d[33]),"+f"(d[34]),"+f"(d[35]),"+f"(d[36]),"+f"(d[37]),"+f"(d[38]),"+f"(d[39]),
      "+f"(d[40]),"+f"(d[41]),"+f"(d[42]),"+f"(d[43]),"+f"(d[44]),"+f"(d[45]),"+f"(d[46]),"+f"(d[47]),"+f"(d[48]),"+f"(d[49]),
      "+f"(d[50]),"+f"(d[51]),"+f"(d[52]),"+f"(d[53]),"+f"(d[54]),"+f"(d[55]),"+f"(d[56]),"+f"(d[57]),"+f"(d[58]),"+f"(d[59]),
      "+f"(d[60]),"+f"(d[61]),"+f"(d[62]),"+f"(d[63]),"+f"(d[64]),"+f"(d[65]),"+f"(d[66]),"+f"(d[67]),"+f"(d[68]),"+f"(d[69]),
      "+f"(d[70]),"+f"(d[71]),"+f"(d[72]),"+f"(d[73]),"+f"(d[74]),"+f"(d[75]),"+f"(d[76]),"+f"(d[77]),"+f"(d[78]),"+f"(d[79]),
      "+f"(d[80]),"+f"(d[81]),"+f"(d[82]),"+f"(d[83]),"+f"(d[84]),"+f"(d[85]),"+f"(d[86]),"+f"(d[87]),"+f"(d[88]),"+f"(d[89]),
      "+f"(d[90]),"+f"(d[91]),"+f"(d[92]),"+f"(d[93]),"+f"(d[94]),"+f"(d[95])
    : "r"(da),"r"(db),"r"(DESC_HI),"r"(sd));
}
__device__ __forceinline__ void mma_ss(float (&d)[64], uint32_t da, uint32_t db, int sd) {
  asm volatile("{\n.reg .pred p;\n.reg .b64 da, db;\nsetp.ne.b32 p, %67, 0;\nmov.b64 da, {%64, %66};\nmov.b64 db, {%65, %66};\n"
    "wgmma.mma_async.sync.aligned.m64n128k16.f32.bf16.bf16 "
    "{%0,%1,%2,%3,%4,%5,%6,%7,%8,%9,%10,%11,%12,%13,%14,%15,%16,%17,%18,%19,%20,%21,%22,%23,%24,%25,%26,%27,%28,%29,%30,%31,%32,%33,%34,%35,%36,%37,%38,%39,%40,%41,%42,%43,%44,%45,%46,%47,%48,%49,%50,%51,%52,%53,%54,%55,%56,%57,%58,%59,%60,%61,%62,%63}, "
    "da, db, p, 1, 1, 0, 1;\n}\n"
    : "+f"(d[0]),"+f"(d[1]),"+f"(d[2]),"+f"(d[3]),"+f"(d[4]),"+f"(d[5]),"+f"(d[6]),"+f"(d[7]),"+f"(d[8]),"+f"(d[9]),
      "+f"(d[10]),"+f"(d[11]),"+f"(d[12]),"+f"(d[13]),"+f"(d[14]),"+f"(d[15]),"+f"(d[16]),"+f"(d[17]),"+f"(d[18]),"+f"(d[19]),
      "+f"(d[20]),"+f"(d[21]),"+f"(d[22]),"+f"(d[23]),"+f"(d[24]),"+f"(d[25]),"+f"(d[26]),"+f"(d[27]),"+f"(d[28]),"+f"(d[29]),
      "+f"(d[30]),"+f"(d[31]),"+f"(d[32]),"+f"(d[33]),"+f"(d[34]),"+f"(d[35]),"+f"(d[36]),"+f"(d[37]),"+f"(d[38]),"+f"(d[39]),
      "+f"(d[40]),"+f"(d[41]),"+f"(d[42]),"+f"(d[43]),"+f"(d[44]),"+f"(d[45]),"+f"(d[46]),"+f"(d[47]),"+f"(d[48]),"+f"(d[49]),
      "+f"(d[50]),"+f"(d[51]),"+f"(d[52]),"+f"(d[53]),"+f"(d[54]),"+f"(d[55]),"+f"(d[56]),"+f"(d[57]),"+f"(d[58]),"+f"(d[59]),
      "+f"(d[60]),"+f"(d[61]),"+f"(d[62]),"+f"(d[63])
    : "r"(da),"r"(db),"r"(DESC_HI),"r"(sd));
}
__device__ __forceinline__ void mma_rs_qk(float (&d)[32], uint32_t a0, uint32_t a1, uint32_t a2, uint32_t a3, uint32_t db, int sd) {
  asm volatile("{\n.reg .pred p;\n.reg .b64 db;\nsetp.ne.b32 p, %38, 0;\nmov.b64 db, {%36, %37};\n"
    "wgmma.mma_async.sync.aligned.m64n64k16.f32.bf16.bf16 "
    "{%0,%1,%2,%3,%4,%5,%6,%7,%8,%9,%10,%11,%12,%13,%14,%15,%16,%17,%18,%19,%20,%21,%22,%23,%24,%25,%26,%27,%28,%29,%30,%31}, "
    "{%32,%33,%34,%35}, db, p, 1, 1, 0;\n}\n"
    : "+f"(d[0]),"+f"(d[1]),"+f"(d[2]),"+f"(d[3]),"+f"(d[4]),"+f"(d[5]),"+f"(d[6]),"+f"(d[7]),"+f"(d[8]),"+f"(d[9]),
      "+f"(d[10]),"+f"(d[11]),"+f"(d[12]),"+f"(d[13]),"+f"(d[14]),"+f"(d[15]),"+f"(d[16]),"+f"(d[17]),"+f"(d[18]),"+f"(d[19]),
      "+f"(d[20]),"+f"(d[21]),"+f"(d[22]),"+f"(d[23]),"+f"(d[24]),"+f"(d[25]),"+f"(d[26]),"+f"(d[27]),"+f"(d[28]),"+f"(d[29]),
      "+f"(d[30]),"+f"(d[31])
    : "r"(a0),"r"(a1),"r"(a2),"r"(a3),"r"(db),"r"(DESC_HI64),"r"(sd));
}
__device__ __forceinline__ void mma_rs_pv(float (&d)[20], uint32_t a0, uint32_t a1, uint32_t a2, uint32_t a3, uint32_t db, int sd) {
  asm volatile("{\n.reg .pred p;\n.reg .b64 db;\nsetp.ne.b32 p, %26, 0;\nmov.b64 db, {%24, %25};\n"
    "wgmma.mma_async.sync.aligned.m64n40k16.f32.bf16.bf16 "
    "{%0,%1,%2,%3,%4,%5,%6,%7,%8,%9,%10,%11,%12,%13,%14,%15,%16,%17,%18,%19}, "
    "{%20,%21,%22,%23}, db, p, 1, 1, 1;\n}\n"
    : "+f"(d[0]),"+f"(d[1]),"+f"(d[2]),"+f"(d[3]),"+f"(d[4]),"+f"(d[5]),"+f"(d[6]),"+f"(d[7]),"+f"(d[8]),"+f"(d[9]),
      "+f"(d[10]),"+f"(d[11]),"+f"(d[12]),"+f"(d[13]),"+f"(d[14]),"+f"(d[15]),"+f"(d[16]),"+f"(d[17]),"+f"(d[18]),"+f"(d[19])
    : "r"(a0),"r"(a1),"r"(a2),"r"(a3),"r"(db),"r"(DESC_HI64),"r"(sd));
}

__device__ __forceinline__ void wg_fence() { asm volatile("wgmma.fence.sync.aligned;" ::: "memory"); }
__device__ __forceinline__ void wg_commit() { asm volatile("wgmma.commit_group.sync.aligned;" ::: "memory"); }
template <int N> __device__ __forceinline__ void wg_wait() { asm volatile("wgmma.wait_group.sync.aligned %0;" ::"n"(N) : "memory"); }
template <int LO, int HI, int N> __device__ __forceinline__ void pin(float (&a)[N]) {
#pragma unroll
  for (int i = LO; i < HI; i++) asm volatile("" : "+f"(a[i])::"memory");
}

__device__ __forceinline__ void mbar_init(uint32_t a, uint32_t cnt) {
  asm volatile("mbarrier.init.shared::cta.b64 [%0], %1;" ::"r"(a), "r"(cnt) : "memory");
}
__device__ __forceinline__ bool mbar_try(uint32_t a, uint32_t ph) {
  uint32_t ok;
  asm volatile("{\n.reg .pred p;\nmbarrier.try_wait.parity.shared::cta.b64 p, [%1], %2;\nselp.u32 %0, 1, 0, p;\n}"
               : "=r"(ok) : "r"(a), "r"(ph) : "memory");
  return ok;
}
__device__ __forceinline__ void mbar_wait_trap(uint32_t a, uint32_t ph) {
  int n = 0;
  while (!mbar_try(a, ph))
    if (++n > SPIN_LIMIT) __trap();
}
__device__ __forceinline__ void mbar_wait(uint32_t a, uint32_t ph) {
  if (!mbar_try(a, ph)) {
    int n = 0;
    while (!mbar_try(a, ph) && ++n < SPIN_LIMIT) {}
  }
}
__device__ __forceinline__ void mbar_expect(uint32_t a, uint32_t bytes) {
  asm volatile("{\n.reg .pred p;\nelect.sync _|p, 0xffffffff;\n@p mbarrier.arrive.expect_tx.shared::cta.b64 _, [%0], %1;\n}" ::"r"(a), "r"(bytes) : "memory");
}
__device__ __forceinline__ void mbar_arrive(uint32_t a) {
  asm volatile("mbarrier.arrive.shared::cta.b64 _, [%0];" ::"r"(a) : "memory");
}
__device__ __forceinline__ void mbar_arrive_cluster_if(uint32_t a, bool p) {
  asm volatile("{\n.reg .pred p;\nsetp.ne.b32 p, %1, 0;\n@p mbarrier.arrive.shared::cluster.b64 _, [%0];\n}"
               ::"r"(a), "r"((int)p) : "memory");
}
__device__ __forceinline__ void tma2d(uint32_t dst, const CUtensorMap* m, int c0, int c1, uint32_t bar) {
  asm volatile("{\n.reg .pred p;\nelect.sync _|p, 0xffffffff;\n@p cp.async.bulk.tensor.2d.shared::cluster.global.mbarrier::complete_tx::bytes [%0], [%1, {%2, %3}], [%4];\n}"
               ::"r"(dst), "l"(m), "r"(c0), "r"(c1), "r"(bar) : "memory");
}
__device__ __forceinline__ void tma2d_mc(uint32_t dst, const CUtensorMap* m, int c0, int c1, uint32_t bar) {
  asm volatile("{\n.reg .pred p;\nelect.sync _|p, 0xffffffff;\n@p cp.async.bulk.tensor.2d.shared::cluster.global.mbarrier::complete_tx::bytes.multicast::cluster"
               " [%0], [%1, {%2, %3}], [%4], %5;\n}"
               ::"r"(dst), "l"(m), "r"(c0), "r"(c1), "r"(bar), "h"((uint16_t)3) : "memory");
}
__device__ __forceinline__ void tma5d_mc(uint32_t dst, const CUtensorMap* m, int c2, int c4, uint32_t bar) {
  asm volatile("{\n.reg .pred p;\nelect.sync _|p, 0xffffffff;\n@p cp.async.bulk.tensor.5d.shared::cluster.global.mbarrier::complete_tx::bytes.multicast::cluster"
               " [%0], [%1, {%2, %2, %3, %2, %4}], [%5], %6;\n}"
               ::"r"(dst), "l"(m), "r"(0), "r"(c2), "r"(c4), "r"(bar), "h"((uint16_t)3) : "memory");
}
__device__ __forceinline__ void tma2d_store(const CUtensorMap* m, int c0, int c1, uint32_t src) {
  asm volatile("cp.async.bulk.tensor.2d.global.shared::cta.bulk_group [%0, {%1, %2}], [%3];"
               ::"l"(m), "r"(c0), "r"(c1), "r"(src) : "memory");
}
__device__ __forceinline__ void wait_counter(int idx, unsigned target) {
  const unsigned* p = g_cnt + idx * CNT_STRIDE;
  unsigned v;
  int n = 0;
  while (true) {
    asm volatile("ld.acquire.gpu.global.u32 %0, [%1];" : "=r"(v) : "l"(p) : "memory");
    if (v >= target) break;
    if (++n > SPIN_LIMIT) __trap();
  }
  asm volatile("fence.proxy.async.global;" ::: "memory");
}
__device__ __forceinline__ void wait_flag(uint32_t& ready, int idx, int bit, unsigned target) {
  if (ready >> bit & 1) return;
  const unsigned* p = g_cnt + idx * CNT_STRIDE + (threadIdx.x & 31);
  int n = 0;
  do {
    unsigned v;
    asm volatile("ld.acquire.gpu.global.u32 %0, [%1];" : "=r"(v) : "l"(p) : "memory");
    ready = __ballot_sync(~0u, v >= target);
    if (++n > SPIN_LIMIT) __trap();
  } while (!(ready >> bit & 1));
  __syncwarp();
  asm volatile("fence.proxy.async.global;" ::: "memory");
}
__device__ __forceinline__ uint32_t pack2(float lo, float hi) {
  uint32_t r;
  asm("cvt.rn.bf16x2.f32 %0, %1, %2;" : "=r"(r) : "f"(hi), "f"(lo));
  return r;
}
__device__ __forceinline__ float bf16r(float x) { return __bfloat162float(__float2bfloat16_rn(x)); }
__device__ __forceinline__ float silu(float a, float hs) {
  float t;
  asm("tanh.approx.f32 %0, %1;" : "=f"(t) : "f"(0.5f * a));
  const float u = a * hs;
  return fmaf(u, t, u);
}
__device__ __forceinline__ void stg128(void* p, uint32_t a, uint32_t b, uint32_t c, uint32_t d) {
  asm volatile("st.global.v4.b32 [%0], {%1, %2, %3, %4};" ::"l"(p), "r"(a), "r"(b), "r"(c), "r"(d) : "memory");
}

template <int BASE, int NG, int N>
__device__ __forceinline__ void store_h(float (&acc)[N], __nv_bfloat16* p, float hs0, float hs1) {
#pragma unroll
  for (int G = 0; G < NG; G++) {
    uint32_t lo[4], hi[4];
#pragma unroll
    for (int j = 0; j < 4; j++) {
      const int b = BASE + 16 * G + 4 * j;
      lo[j] = pack2(silu(acc[b], hs0), silu(acc[b + 1], hs0));
      hi[j] = pack2(silu(acc[b + 2], hs1), silu(acc[b + 3], hs1));
    }
    stg128(p + 32 * G, lo[0], lo[1], lo[2], lo[3]);
    stg128(p + 32 * G + 8 * FF, hi[0], hi[1], hi[2], hi[3]);
  }
}

struct Cons {
  uint32_t a1, b1;
  uint32_t a2, b2;
  uint32_t v16, k16;
  uint32_t bar;
  uint32_t rel;
  bool is_rel;
  __device__ __forceinline__ void wait_full(int gs) const { mbar_wait(bar + BAR_FULL + 8 * (gs & 3), (gs >> 2) & 1); }
  __device__ __forceinline__ void wait_full2(int slot, int ph) const { mbar_wait(bar + BAR_FULL2 + 8 * slot, ph); }
  __device__ __forceinline__ void release(int gs, bool p = true) const { mbar_arrive_cluster_if(rel + BAR_EMPTY + 8 * (gs & 3), is_rel && p); }
  __device__ __forceinline__ void release2(int slot, bool p = true) const { mbar_arrive_cluster_if(rel + BAR_EMPTY2 + 8 * slot, is_rel && p); }
};

__device__ __forceinline__ void issue_pv(const Cons& c, float (&O)[20], const uint32_t (&P)[16], int slot, int sd) {
  const uint32_t v = c.v16 + slot * (512 * V_STEP);
#pragma unroll
  for (int kk = 0; kk < 4; kk++)
    mma_rs_pv(O, P[4 * kk], P[4 * kk + 1], P[4 * kk + 2], P[4 * kk + 3], v + kk * (64 * V_STEP), kk > 0 || sd);
}
template <int NG, class G>
__device__ __forceinline__ void issue_batch(const Cons& c, float (&S)[32], const uint32_t (&Q)[8], int sk,
                                            float (&O)[20], const uint32_t (&P)[16], int sv, int sd, G g) {
  const uint32_t k = c.k16 + sk * 512;
  wg_fence();
  issue_pv(c, O, P, sv, sd);
  mma_rs_qk(S, Q[0], Q[1], Q[2], Q[3], k, 0);
  mma_rs_qk(S, Q[4], Q[5], Q[6], Q[7], k + 2, 1);
  wg_commit();
#pragma unroll
  for (int i = 0; i < NG; i++) g(i);
  wg_commit();
}
__device__ __forceinline__ void gstep(float (&acc)[104], uint32_t da, uint32_t db, int kk, int sd = 1) {
  mma_ss(acc, da + kk * 2, db + kk * 128, sd);
}
__device__ __forceinline__ void gstep(float (&acc)[64], uint32_t da, uint32_t db, int kk) {
  mma_ss(acc, da + kk * 2, db + (kk >> 1) * 512 + (kk & 1) * 128, 1);
}
__device__ __forceinline__ uint32_t opaque(uint32_t x) { return __shfl_sync(~0u, x, 0); }
template <class F>
__device__ __forceinline__ void exp_phase(float (&S)[32], uint32_t (&P)[16], F done) {
  float E[32];
  wg_wait<1>();
  pin<0, 32>(S);
  done();
#pragma unroll
  for (int i = 0; i < 32; i++) asm volatile("ex2.approx.ftz.f32 %0, %1;" : "=f"(E[i]) : "f"(S[i]));
#pragma unroll
  for (int i = 0; i < 16; i++) P[i] = pack2(E[2 * i], E[2 * i + 1]);
}
__device__ __forceinline__ void store_head(const float* O, float s0, float s1, __nv_bfloat16* p) {
  stg128(p, pack2(O[0] * s0, O[1] * s0), pack2(O[4] * s0, O[5] * s0), pack2(O[8] * s0, O[9] * s0), pack2(O[12] * s0, O[13] * s0));
  stg128(p + 8 * DM, pack2(O[2] * s1, O[3] * s1), pack2(O[6] * s1, O[7] * s1), pack2(O[10] * s1, O[11] * s1), pack2(O[14] * s1, O[15] * s1));
}
__device__ __forceinline__ uint32_t finalize_head(const float (&O)[20], __nv_bfloat16* p, float g0, float g1) {
  store_head(O, __fdividef(g0, O[16]), __fdividef(g1, O[18]), p);
  float z = 0.f;
#pragma unroll
  for (int i = 0; i < 16; i++) z = fmaf(O[i], 0.f, z);
  const bool ok = O[16] >= L_MIN && O[16] <= L_MAX && O[18] >= L_MIN && O[18] <= L_MAX && z == 0.f;
  return __any_sync(~0u, !ok) ? 1u : 0u;
}
__device__ __forceinline__ void mma16816(float* d, uint32_t a0, uint32_t a1, uint32_t a2, uint32_t a3, uint32_t b0, uint32_t b1) {
  asm("mma.sync.aligned.m16n8k16.row.col.f32.bf16.bf16.f32 {%0,%1,%2,%3}, {%4,%5,%6,%7}, {%8,%9}, {%0,%1,%2,%3};"
      : "+f"(d[0]), "+f"(d[1]), "+f"(d[2]), "+f"(d[3]) : "r"(a0), "r"(a1), "r"(a2), "r"(a3), "r"(b0), "r"(b1));
}
__device__ __forceinline__ void redo_heads(uint32_t mask, const uint32_t (&Qa)[8], const uint32_t (&Qb)[8],
                                           __nv_bfloat16* op, float g0, float g1) {
  const int lane = threadIdx.x & 31, t4 = lane & 3, rq = lane >> 2;
  const uint32_t* K = reinterpret_cast<const uint32_t*>(g_KV + SEQ * 32) + rq * 16 + t4;
  const unsigned short* V = reinterpret_cast<const unsigned short*>(g_KV) + 2 * t4 * 32 + rq;
#pragma unroll 1
  for (int h = 0; h < 2; h++) {
    if (!(mask >> h & 1)) continue;
    uint32_t q[8];
#pragma unroll
    for (int i = 0; i < 8; i++) q[i] = h ? Qb[i] : Qa[i];
    float R[16], m0 = -INFINITY, m1 = -INFINITY, l0 = 0.f, l1 = 0.f;
#pragma unroll
    for (int i = 0; i < 16; i++) R[i] = 0.f;
#pragma unroll 1
    for (int kb = 0; kb < SEQ; kb += 16) {
      float s[8];
#pragma unroll
      for (int n = 0; n < 2; n++) {
        const uint32_t* k = K + (kb + 8 * n) * 16;
        s[4 * n] = s[4 * n + 1] = s[4 * n + 2] = s[4 * n + 3] = 0.f;
        mma16816(s + 4 * n, q[0], q[1], q[2], q[3], __ldcg(k), __ldcg(k + 4));
        mma16816(s + 4 * n, q[4], q[5], q[6], q[7], __ldcg(k + 8), __ldcg(k + 12));
      }
      float n0 = fmaxf(fmaxf(s[0], s[1]), fmaxf(s[4], s[5])), n1 = fmaxf(fmaxf(s[2], s[3]), fmaxf(s[6], s[7]));
#pragma unroll
      for (int o = 1; o < 4; o <<= 1) {
        n0 = fmaxf(n0, __shfl_xor_sync(~0u, n0, o));
        n1 = fmaxf(n1, __shfl_xor_sync(~0u, n1, o));
      }
      n0 = fmaxf(n0, m0);
      n1 = fmaxf(n1, m1);
      const float a0 = exp2f(m0 - n0), a1 = exp2f(m1 - n1);
      m0 = n0;
      m1 = n1;
#pragma unroll
      for (int i = 0; i < 8; i++) s[i] = exp2f(s[i] - (i & 2 ? n1 : n0));
      l0 = l0 * a0 + (s[0] + s[1]) + (s[4] + s[5]);
      l1 = l1 * a1 + (s[2] + s[3]) + (s[6] + s[7]);
      const uint32_t p0 = pack2(s[0], s[1]), p1 = pack2(s[2], s[3]), p2 = pack2(s[4], s[5]), p3 = pack2(s[6], s[7]);
#pragma unroll
      for (int j = 0; j < 4; j++) {
        const unsigned short* v = V + kb * 32 + 8 * j;
        R[4 * j] *= a0;
        R[4 * j + 1] *= a0;
        R[4 * j + 2] *= a1;
        R[4 * j + 3] *= a1;
        mma16816(R + 4 * j, p0, p1, p2, p3, __ldcg(v) | (uint32_t)__ldcg(v + 32) << 16,
                 __ldcg(v + 256) | (uint32_t)__ldcg(v + 288) << 16);
      }
    }
#pragma unroll
    for (int o = 1; o < 4; o <<= 1) {
      l0 += __shfl_xor_sync(~0u, l0, o);
      l1 += __shfl_xor_sync(~0u, l1, o);
    }
    store_head(R, __fdividef(g0, l0), __fdividef(g1, l1), op + 32 * h);
  }
}
__device__ __forceinline__ int tid_now() {
  int t;
  asm volatile("mov.u32 %0, %%tid.x;" : "=r"(t));
  return t - 128;
}
__device__ __forceinline__ __nv_bfloat16* row_ptr(__nv_bfloat16* base, int ld, int r, int col) {
  const int t = tid_now();
  return base + (128 * r + (t >> 5) * 16 + ((t & 31) >> 2)) * ld + col + 8 * (t & 3);
}
__device__ __forceinline__ void put_strip(uint32_t d, const uint4& kv, uint32_t g) {
  asm volatile("st.shared.v4.b32 [%0], {%1,%2,%3,%4};" ::"r"(d), "r"(kv.x), "r"(kv.y), "r"(kv.z), "r"(kv.w) : "memory");
  asm volatile("st.shared.v4.b32 [%0], {%1,%1,%1,%1};" ::"r"(d ^ 16), "r"(g * 0x10001u) : "memory");
}
__device__ __forceinline__ void signal(uint32_t bar, int ev) {
  __syncwarp();
  if ((threadIdx.x & 31) == 0) mbar_arrive(bar + BAR_SIG + 8 * ev);
}

__global__ void __cluster_dims__(2, 1, 1) __launch_bounds__(384, 1)
fused_kernel(const __grid_constant__ Maps maps, const __grid_constant__ Ptrs ptrs,
             const __nv_bfloat16* __restrict__ gate_w, uint8_t* __restrict__ out) {
  extern __shared__ __align__(1024) uint8_t smem_raw[];
  const uint32_t sb = ((uint32_t)__cvta_generic_to_shared(smem_raw) + 1023u) & ~1023u;
  const uint32_t bar = sb + BAR_OFF;
  const int warp = __shfl_sync(~0u, (int)(threadIdx.x >> 5), 0);
  const int lane = threadIdx.x & 31;
  const int rank = blockIdx.x & 1;
  const int cid = blockIdx.x >> 1;
  const int rp = cid & 7, c = cid >> 3;
  const int r = 2 * rp + rank;

  const uint4* wkv = reinterpret_cast<const uint4*>((c < 4 ? ptrs.wv : ptrs.wk) + 16 * (c & 3));
  const unsigned short* gp = reinterpret_cast<const unsigned short*>(gate_w);
  uint4 kv_first;
  uint32_t g_first;
  if (warp >= 4) {
    kv_first = __ldg(wkv + 4 * (threadIdx.x - 128));
    g_first = __ldg(gp + threadIdx.x - 128);
  }
  if (threadIdx.x >= 64 && threadIdx.x < 64 + 9)
    asm volatile("prefetch.tensormap [%0];" ::"l"(&maps.x + (threadIdx.x - 64)) : "memory");
  if (warp == 0) {
    if (lane == 0) {
#pragma unroll
      for (int i = 0; i < 4; i++) mbar_init(bar + BAR_FULL + 8 * i, 2);
    }
    __syncwarp();
#pragma unroll
    for (int gs = 0; gs < N_FIRST; gs++) {
      const uint32_t full = bar + BAR_FULL + 8 * gs;
      mbar_expect(full, 40960);
      tma2d(sb + A1_OFF + gs * 16384, &maps.x, 64 * gs, 128 * r, full);
#pragma unroll
      for (int h = 0; h < 2; h++) {
        const uint32_t dst = sb + B1_OFF + gs * 8192 + 4096 * h;
        tma2d(dst, &maps.wq, 128 * c, 64 * gs + 32 * h, full);
        tma2d(dst + 32768, &maps.w1, 448 * c, 64 * gs + 32 * h, full);
        tma2d(dst + 65536, &maps.w1, 448 * c + 64, 64 * gs + 32 * h, full);
      }
    }
    if (lane == 0) asm volatile("fence.mbarrier_init.release.cluster;" ::: "memory");
  }
  if (threadIdx.x == 32) {
#pragma unroll
    for (int i = 0; i < 4; i++) mbar_init(bar + BAR_EMPTY + 8 * i, 4);
#pragma unroll
    for (int i = 0; i < 5; i++) mbar_init(bar + BAR_SIG + 8 * i, 8);
#pragma unroll
    for (int i = 0; i < 6; i++) {
      mbar_init(bar + BAR_FULL2 + 8 * i, 1);
      mbar_init(bar + BAR_EMPTY2 + 8 * i, 4);
    }
    mbar_init(bar + BAR_OWN, 1);
    asm volatile("fence.mbarrier_init.release.cluster;" ::: "memory");
  }
  __syncthreads();
  asm volatile("barrier.cluster.arrive.relaxed.aligned;" ::: "memory");
  if (warp >= 4) {
    asm volatile("setmaxnreg.inc.sync.aligned.u32 232;");
    put_strip(sb + KV_OFF + (threadIdx.x - 128) * 128 + ((lane & 7) << 4), kv_first, g_first);
    asm volatile("st.shared.b32 [%0], %1;" ::"r"(sb + ONES_OFF + 4 * (threadIdx.x - 128)), "r"(0x3f803f80u) : "memory");
    asm volatile("fence.proxy.async.shared::cta;\nbar.sync 3, 256;" ::: "memory");
    asm volatile("barrier.cluster.wait.aligned;" ::: "memory");
    const int w = (warp >> 2) - 1;
    const int wq = warp & 3;
    const int tid = threadIdx.x & 127;
    const int t4 = lane & 3;
    Cons cs;
    const uint32_t so = sb & 0x3FFFFu;
    cs.a1 = opaque(((so + A1_OFF + w * 8192) >> 4) + LBO_A);
    cs.b1 = opaque(((so + B1_OFF) >> 4) + LBO_B1);
    cs.a2 = opaque(((so + w * 8192) >> 4) + LBO_A);
    cs.b2 = opaque(((so + 16384) >> 4) + LBO_B2);
    cs.v16 = opaque(((so + KV_OFF) >> 4) + (((ONES_OFF - KV_OFF) >> 4) << 16));
    cs.k16 = opaque(((so + KV_OFF + 4096) >> 4) + LBO_A);
    cs.bar = opaque(bar);
    cs.is_rel = (tid == 0) || (tid == 32);
    asm("mapa.shared::cluster.u32 %0, %1, %2;" : "=r"(cs.rel) : "r"(bar), "r"(wq & 1));

    float acc[104], acc2[64], S[32], Oa[20], Ob[20];
    uint32_t P[16], Qa[8], Qb[8];

#pragma unroll 1
    for (int gs = 0; gs < GS_F1; gs++) {
      cs.wait_full(gs);
      wg_fence();
#pragma unroll
      for (int kk = 0; kk < 4; kk++)
        mma_n208(acc, cs.a1 + (gs & 3) * 1024 + kk * 2, cs.b1 + (gs & 3) * 512 + kk * 128, kk > 0 || gs > 0);
      wg_commit();
      wg_wait<1>();
      cs.release(gs - 1, gs > 0);
    }
    wg_wait<0>();
    cs.release(GS_F1 - 1);
    pin<0, 104>(acc);
    {
      const uint32_t ka = sb + (64 * w + 16 * wq + (lane >> 2)) * 16 + 4 * t4;
      asm volatile("st.shared.b32 [%0], %1;\nst.shared.b32 [%0+128], %2;\nfence.proxy.async.shared::cta;"
                   ::"r"(ka), "r"(pack2(acc[96], acc[97])), "r"(pack2(acc[98], acc[99])) : "memory");
      signal(bar, 0);
    }
    const float g0 = bf16r(__fdividef(1.f, 1.f + __expf(-bf16r(acc[100]))));
    const float g1 = bf16r(__fdividef(1.f, 1.f + __expf(-bf16r(acc[102]))));
#pragma unroll
    for (int i = 0; i < 8; i++) {
      Qa[i] = pack2(acc[2 * i] * Q_SCALE, acc[2 * i + 1] * Q_SCALE);
      Qb[i] = pack2(acc[16 + 2 * i] * Q_SCALE, acc[17 + 2 * i] * Q_SCALE);
    }
    float F[64];
#pragma unroll
    for (int i = 0; i < 64; i++) F[i] = acc[32 + i];
    pin<0, 64>(F);

    auto nop = [] {};
#pragma unroll
    for (int gs = GS_F1; gs < GS_F1 + N_PURE; gs++) {
      cs.wait_full(gs);
      wg_fence();
#pragma unroll
      for (int kk = 0; kk < 4; kk++) gstep(acc, cs.a1 + (gs & 3) * 1024, cs.b1 + (gs & 3) * 512, kk, kk > 0 || gs > GS_F1);
      wg_commit();
      if (gs == GS_F1) store_h<0, 1>(F, row_ptr(g_H, FF, r, 448 * c), 0.5f * bf16r(1.f - g0), 0.5f * bf16r(1.f - g1));
      if (gs == GS_F1 + 1) store_h<16, 1>(F, row_ptr(g_H, FF, r, 448 * c + 32), 0.5f * bf16r(1.f - g0), 0.5f * bf16r(1.f - g1));
      if (gs == GS_F1 + 2) store_h<32, 1>(F, row_ptr(g_H, FF, r, 448 * c + 64), 0.5f * bf16r(1.f - g0), 0.5f * bf16r(1.f - g1));
      if (gs == GS_F1 + 3) store_h<48, 1>(F, row_ptr(g_H, FF, r, 448 * c + 96), 0.5f * bf16r(1.f - g0), 0.5f * bf16r(1.f - g1));
      wg_wait<1>();
      cs.release(gs - 1, gs > GS_F1);
    }
#pragma unroll
    for (int i = 0; i < 16; i++) P[i] = 0u;
#pragma unroll
    for (int i = 0; i < 20; i++) { Oa[i] = 0.f; Ob[i] = 0.f; }
    int gs = GS_F1 + N_PURE;
    uint32_t da = cs.a1 + (gs & 3) * 1024, db = cs.b1 + (gs & 3) * 512;
    int vc = gs & 3, vp = vc;
    cs.wait_full(gs);
#pragma unroll 1
    for (int tile = 0; tile < 2; tile++) {
#pragma unroll 1
      for (; gs < GS_F1 + 16 + 16 * tile; gs++) {
        issue_batch<2>(cs, S, Qa, vc, Ob, P, vp, gs != GS_F1 + N_PURE + 1,
                       [&](int i) { gstep(acc, da, db, i, i > 0 || gs != GS_F1 + 16); });
        exp_phase(S, P, [&] { cs.release(gs - 1); });

        issue_batch<2>(cs, S, Qb, vc, Oa, P, vc, gs != GS_F1 + N_PURE, [&](int i) { gstep(acc, da, db, 2 + i); });
        const int sn = (gs + 1) & 3;
        da = cs.a1 + sn * 1024;
        db = cs.b1 + sn * 512;
        vp = vc;
        vc = sn;
        if (gs + 1 < GS_F2) cs.wait_full(gs + 1);
        exp_phase(S, P, nop);
      }
      wg_wait<0>();
      cs.release(gs - 1, tile == 1);
      pin<0, 96>(acc);
      store_h<32, 4>(acc, row_ptr(g_H, FF, r, 448 * c + 192 + 128 * tile), 0.5f * bf16r(1.f - g0), 0.5f * bf16r(1.f - g1));
      if (tile == 1) break;
      store_h<0, 2>(acc, row_ptr(g_H, FF, r, 448 * c + 128), 0.5f * bf16r(1.f - g0), 0.5f * bf16r(1.f - g1));
      signal(bar, 1);
    }
    signal(bar, 2);

    uint32_t Qn[16];
#pragma unroll
    for (int i = 0; i < 16; i++) Qn[i] = pack2(acc[2 * i] * Q_SCALE, acc[2 * i + 1] * Q_SCALE);
#pragma unroll
    for (int i = 0; i < 64; i++) acc2[i] = 0.f;
    int s0 = 0, ph = 0, t = T_F2;
    da = cs.a2;
    db = cs.b2;
    cs.wait_full2(0, 0);
#pragma unroll 1
    for (int pass = 0; pass < 2; pass++) {
#pragma unroll 1
      for (; t < 32 + 32 * pass; t += 2) {
        auto gblock = [&](int q) { gstep(acc2, da + (q >> 2) * 2048, db + (q >> 2) * 2048, q & 3); };
        issue_batch<3>(cs, S, Qa, vc, Ob, P, vp, 1, [&](int i) { gblock(0 + i); });
        cs.wait_full2(s0 + 1, ph);
        exp_phase(S, P, [&] { cs.release2(5 - s0, t > T_F2); });

        issue_batch<3>(cs, S, Qb, vc, Oa, P, vc, t != 32, [&](int i) { gblock(3 + i); });
        cs.wait_full2(s0 + 2, ph);
        exp_phase(S, P, nop);

        issue_batch<3>(cs, S, Qa, vc + 1, Ob, P, vc, t != 32, [&](int i) { gblock(6 + i); });
        exp_phase(S, P, [&] { cs.release2(s0); });

        issue_batch<3>(cs, S, Qb, vc + 1, Oa, P, vc + 1, 1, [&](int i) { gblock(9 + i); });
        const int s1 = s0 + 1;
        if (s0) ph ^= 1;
        s0 = 3 - s0;
        da = cs.a2 + s0 * 2048;
        db = cs.b2 + s0 * 2048;
        vp = vc + 1;
        vc = (t + 2 + N_PURE) & 3;
        cs.wait_full2(s0, ph);
        exp_phase(S, P, [&] { cs.release2(s1); pin<0, 20>(Oa); });
      }
      wg_fence();
      issue_pv(cs, Ob, P, vp, 1);
      wg_commit();
      __nv_bfloat16* op = row_ptr(g_O, DM, r, 128 * c + 64 * pass);
      uint32_t redo = finalize_head(Oa, op, g0, g1);
      wg_wait<0>();
      pin<0, 20>(Ob);
      redo |= finalize_head(Ob, op + 32, g0, g1) << 1;
      if (redo) redo_heads(redo, Qa, Qb, op, g0, g1);
      signal(bar, 3 + pass);
#pragma unroll
      for (int i = 0; i < 8; i++) { Qa[i] = Qn[i]; Qb[i] = Qn[8 + i]; }
    }
    static_assert(U_TAIL < 64, "the second O half is needed at stage 64");
    {
      int slot = U_TAIL % 6, prev = (U_TAIL + 5) % 6;
      ph = (U_TAIL / 6) & 1;
#pragma unroll 1
      for (int u = U_TAIL; u < U_END; u++) {
        cs.wait_full2(slot, ph);
        wg_fence();
#pragma unroll
        for (int kk = 0; kk < 4; kk++) gstep(acc2, cs.a2 + slot * 2048, cs.b2 + slot * 2048, kk);
        wg_commit();
        wg_wait<1>();
        cs.release2(prev);
        prev = slot;
        if (++slot == 6) { slot = 0; ph ^= 1; }
      }
    }
    wg_wait<0>();
    asm volatile("barrier.cluster.arrive.relaxed;" ::: "memory");
    pin<0, 64>(acc2);

    {
      const int m = lane >> 3;
      const int srow = 16 * wq + (m & 1) * 8 + (lane & 7);
      const uint32_t sa = sb + w * 8192 + srow * 128;
#pragma unroll
      for (int j = 0; j < 8; j++) {
        const uint32_t a = sa + (j >> 2) * 32768 + (((2 * (j & 3) + (m >> 1)) ^ (lane & 7)) << 4);
        asm volatile("stmatrix.sync.aligned.m8n8.x4.shared.b16 [%0], {%1,%2,%3,%4};" ::"r"(a),
                     "r"(pack2(acc2[8 * j], acc2[8 * j + 1])), "r"(pack2(acc2[8 * j + 2], acc2[8 * j + 3])),
                     "r"(pack2(acc2[8 * j + 4], acc2[8 * j + 5])), "r"(pack2(acc2[8 * j + 6], acc2[8 * j + 7])) : "memory");
      }
      __syncwarp();
      const int lr = lane >> 3, lc = lane & 7;
      uint8_t* gp = out + (size_t)(128 * r + 64 * w + 16 * wq + lr) * (DM * 2) + 256 * c + 16 * lc;
#pragma unroll
      for (int i = 0; i < 8; i++) {
        const int rr = 4 * (i & 3) + lr;
        uint32_t v[4];
        asm volatile("ld.shared.v4.b32 {%0,%1,%2,%3}, [%4];" : "=r"(v[0]), "=r"(v[1]), "=r"(v[2]), "=r"(v[3])
                     : "r"(sb + w * 8192 + (16 * wq + rr) * 128 + (i >> 2) * 32768 + ((lc ^ (rr & 7)) << 4)) : "memory");
        stg128(gp + (i & 3) * 4 * (DM * 2) + (i >> 2) * 128, v[0], v[1], v[2], v[3]);
      }
    }
    asm volatile("barrier.cluster.wait;" ::: "memory");
  } else {
    asm volatile("setmaxnreg.dec.sync.aligned.u32 40;");
    const int row0 = 128 * r;
    const int kh = 32 * rank;
    if (warp == 3 && lane < 4) mbar_arrive(bar + BAR_FULL + 8 * lane);
    __syncwarp();
    asm volatile("barrier.cluster.wait.aligned;" ::: "memory");
    constexpr uint32_t PH_F1_LAST = ((GS_F2 >> 2) & 1) ^ 1;
    if (warp == 0) {
#pragma unroll 1
      for (int gs = N_FIRST; gs < GS_F2; gs++) {
        const uint32_t full = bar + BAR_FULL + 8 * (gs & 3);
        mbar_wait_trap(bar + BAR_EMPTY + 8 * (gs & 3), ((gs >> 2) & 1) ^ 1);
        mbar_expect(full, 40960);
        tma2d(sb + A1_OFF + (gs & 3) * 16384, &maps.x, 64 * (gs & 15), row0, full);
      }
      int slot = 0, ph = 1, u = 0;
      auto stage = [&](const CUtensorMap* m, int k0) {
        const uint32_t full = bar + BAR_FULL2 + 8 * slot;
        mbar_wait_trap(bar + BAR_EMPTY2 + 8 * slot, ph);
        mbar_expect(full, (u < U_TAIL && slot != 1 && slot != 4) ? 40960 : 32768);
        tma2d(sb + slot * 32768, m, k0, row0, full);
        u++;
        if (++slot == 6) { slot = 0; ph ^= 1; }
      };
      wait_counter(CNT_H + 2 * r, 8);
      stage(&maps.h, 0);
      for (int i = 0; i < 2; i++) mbar_wait_trap(bar + BAR_EMPTY + 8 * i, PH_F1_LAST);
      stage(&maps.h, 64);
      for (int i = 2; i < 4; i++) mbar_wait_trap(bar + BAR_EMPTY + 8 * i, PH_F1_LAST);
      stage(&maps.h, 128);
      mbar_wait_trap(bar + BAR_SIG + 16, 0);
      stage(&maps.h, 192);
      stage(&maps.h, 256);
#pragma unroll 1
      for (int i = 1; i < 8; i++)
#pragma unroll 1
        for (int q = 0; q < 5; q++) stage(&maps.h, 448 * i + 64 * q);
      wait_counter(CNT_H + 2 * r + 1, 8);
#pragma unroll 1
      for (int i = 0; i < 8; i++)
#pragma unroll 1
        for (int q = 0; q < 2; q++) stage(&maps.h, 448 * i + 320 + 64 * q);
      wait_counter(CNT_O + r, 8);
#pragma unroll 1
      for (int i = 0; i < 8; i++) stage(&maps.o, 128 * i);
      mbar_wait_trap(bar + BAR_OWN, 0);
      asm volatile("fence.proxy.async.global;" ::: "memory");
      stage(&maps.o, 128 * c + 64);
      uint32_t ready = 0;
#pragma unroll 1
      for (int i = 1; i < 8; i++) {
        wait_flag(ready, CNT_O2 + r, (c + i) & 7, 1);
        stage(&maps.o, 128 * ((c + i) & 7) + 64);
      }
      unsigned last = 0;
      if (lane == 0) last = atomicAdd(g_cnt + CNT_DONE * CNT_STRIDE, 1u) == 127u;
      if (__shfl_sync(~0u, last, 0))
        for (int i = lane; i < CNT_NUM * CNT_STRIDE; i += 32) g_cnt[i] = 0u;
    } else if (warp == 1) {
#pragma unroll 1
      for (int gs = N_FIRST; gs < GS_F1; gs++) {
        const uint32_t dst = sb + B1_OFF + (gs & 3) * 8192 + 4096 * rank;
        const uint32_t full = bar + BAR_FULL + 8 * (gs & 3);
        const int k0 = 64 * gs + kh;
        mbar_wait_trap(bar + BAR_EMPTY + 8 * (gs & 3), ((gs >> 2) & 1) ^ 1);
        tma2d_mc(dst, &maps.wq, 128 * c, k0, full);
        tma2d_mc(dst + 32768, &maps.w1, 448 * c, k0, full);
        tma2d_mc(dst + 65536, &maps.w1, 448 * c + 64, k0, full);
      }
#pragma unroll 1
      for (int gs = GS_F1; gs < GS_F2; gs++) {
        const uint32_t dst = sb + B1_OFF + (gs & 3) * 8192 + 4096 * rank;
        const uint32_t full = bar + BAR_FULL + 8 * (gs & 3);
        const int k0 = 64 * (gs & 15) + kh;
        const int n0 = 448 * c + 128 + 128 * (gs >> 5);
        mbar_wait_trap(bar + BAR_EMPTY + 8 * (gs & 3), ((gs >> 2) & 1) ^ 1);
        tma2d_mc(dst, gs < 32 ? &maps.w1 : &maps.wq, gs < 32 ? n0 : 128 * c + 64, k0, full);
        tma2d_mc(dst + 32768, &maps.w1, n0 + 64, k0, full);
        tma2d_mc(dst + 65536, &maps.w1, n0 + 128, k0, full);
      }
      int slot = 0, ph = 1;
      auto stage = [&](const CUtensorMap* m, int k0) {
        mbar_wait_trap(bar + BAR_EMPTY2 + 8 * slot, ph);
        tma5d_mc(sb + slot * 32768 + 16384 + 8192 * rank, m, (k0 + kh) >> 3, 2 * c, bar + BAR_FULL2 + 8 * slot);
        if (++slot == 6) { slot = 0; ph ^= 1; }
      };
      stage(&maps.w2, 0);
      for (int i = 0; i < 2; i++) mbar_wait_trap(bar + BAR_EMPTY + 8 * i, PH_F1_LAST);
      stage(&maps.w2, 64);
      for (int i = 2; i < 4; i++) mbar_wait_trap(bar + BAR_EMPTY + 8 * i, PH_F1_LAST);
      stage(&maps.w2, 128);
      mbar_wait_trap(bar + BAR_SIG + 16, 0);
      stage(&maps.w2, 192);
      stage(&maps.w2, 256);
#pragma unroll 1
      for (int i = 1; i < 8; i++)
#pragma unroll 1
        for (int q = 0; q < 5; q++) stage(&maps.w2, 448 * i + 64 * q);
#pragma unroll 1
      for (int i = 0; i < 8; i++)
#pragma unroll 1
        for (int q = 0; q < 2; q++) stage(&maps.w2, 448 * i + 320 + 64 * q);
#pragma unroll 1
      for (int i = 0; i < 8; i++) stage(&maps.wo, 128 * i);
#pragma unroll 1
      for (int i = 0; i < 8; i++) stage(&maps.wo, 128 * ((c + i) & 7) + 64);
    } else if (warp == 3) {
      uint4 kvw[2][2];
      uint32_t gv[2][2];
#pragma unroll
      for (int i = 0; i < 4; i++) {
        kvw[i >> 1][i & 1] = __ldg(wkv + 4 * (256 + 32 * i + lane));
        gv[i >> 1][i & 1] = __ldg(gp + 256 + 32 * i + lane);
      }
#pragma unroll 1
      for (int g2 = 4; g2 < GS_F1; g2 += 2) {
#pragma unroll
        for (int i = 0; i < 2; i++) {
          const int gs = g2 + i;
          const uint32_t d = sb + KV_OFF + (gs & 3) * 8192 + lane * 128 + ((lane & 7) << 4);
          mbar_wait_trap(bar + BAR_EMPTY + 8 * (gs & 3), ((gs >> 2) & 1) ^ 1);
          put_strip(d, kvw[i][0], gv[i][0]);
          put_strip(d + 4096, kvw[i][1], gv[i][1]);
          asm volatile("fence.proxy.async.shared::cta;" ::: "memory");
          __syncwarp();
          if (lane == 0) mbar_arrive(bar + BAR_FULL + 8 * (gs & 3));
          if (gs + 2 < GS_F1) {
#pragma unroll
            for (int h = 0; h < 2; h++) {
              kvw[i][h] = __ldg(wkv + 4 * (64 * (gs + 2) + 32 * h + lane));
              gv[i][h] = __ldg(gp + 64 * (gs + 2) + 32 * h + lane);
            }
          }
        }
      }
      const uint32_t dst = sb + KV_OFF + 2048 * rank;
      uint32_t ready = 0;
#pragma unroll 1
      for (int gs = GS_F1; gs < GS_F2; gs++) {
        const uint32_t full = bar + BAR_FULL + 8 * (gs & 3);
        mbar_wait_trap(bar + BAR_EMPTY + 8 * (gs & 3), ((gs >> 2) & 1) ^ 1);
        if (gs < GS_F1 + N_PURE) {
          if (lane == 0) mbar_arrive(full);
          __syncwarp();
        } else {
          const int t = gs - GS_F1 - N_PURE;
          const int kt = (t + 4 * rp) & 31;
          wait_flag(ready, CNT_KV, kt >> 1, 8);
          mbar_expect(full, 8192);
          tma2d_mc(dst + (gs & 3) * 8192, &maps.kv, 0, 64 * kt + kh, full);
          tma2d_mc(dst + (gs & 3) * 8192 + 4096, &maps.kv, 0, SEQ + 64 * kt + kh, full);
        }
      }
      int slot = 0, ph = 1;
#pragma unroll 1
      for (int t = T_F2; t < 64; t++) {
        if (t < T_F2 + 3) mbar_wait_trap(bar + BAR_EMPTY + 8 * (t - T_F2), PH_F1_LAST);
        if (t == T_F2 + 3) mbar_wait_trap(bar + BAR_EMPTY2, 0);
        const int kt = (t + 4 * rp) & 31;
        wait_flag(ready, CNT_KV, kt >> 1, 8);
        mbar_wait_trap(bar + BAR_EMPTY2 + 8 * slot, ph);
        tma2d_mc(dst + ((t + N_PURE) & 3) * 8192, &maps.kv, 0, 64 * kt + kh, bar + BAR_FULL2 + 8 * slot);
        tma2d_mc(dst + ((t + N_PURE) & 3) * 8192 + 4096, &maps.kv, 0, SEQ + 64 * kt + kh, bar + BAR_FULL2 + 8 * slot);
        slot += (t & 1) ? 1 : 2;
        if (slot == 6) { slot = 0; ph ^= 1; }
      }
    } else {
      mbar_wait_trap(bar + BAR_SIG, 0);
      if (lane == 0) {
        tma2d_store(&maps.kvs, 8 * (c & 3), (c >> 2) * SEQ + row0, sb);
        asm volatile("cp.async.bulk.commit_group;\ncp.async.bulk.wait_group 0;\nfence.proxy.async.global;" ::: "memory");
        asm volatile("red.relaxed.gpu.global.add.u32 [%0], 1;" ::"l"(g_cnt + CNT_KV * CNT_STRIDE + r) : "memory");
      }
      __syncwarp();
#pragma unroll 1
      for (int ev = 1; ev < 5; ev++) {
        mbar_wait_trap(bar + BAR_SIG + 8 * ev, 0);
        const int idx = ev < 3 ? (CNT_H + 2 * r + ev - 1) * CNT_STRIDE : ev == 3 ? (CNT_O + r) * CNT_STRIDE : (CNT_O2 + r) * CNT_STRIDE + c;
        if (lane == 0) asm volatile("red.release.gpu.global.add.u32 [%0], 1;" ::"l"(g_cnt + idx) : "memory");
      }
      if (lane == 0) mbar_arrive(bar + BAR_OWN);
    }
    __syncwarp();
    asm volatile("barrier.cluster.arrive.relaxed;\nbarrier.cluster.wait;" ::: "memory");
  }
}

typedef CUresult (*EncodeFn)(CUtensorMap*, CUtensorMapDataType, cuuint32_t, void*, const cuuint64_t*, const cuuint64_t*,
                             const cuuint32_t*, const cuuint32_t*, CUtensorMapInterleave, CUtensorMapSwizzle,
                             CUtensorMapL2promotion, CUtensorMapFloatOOBfill);

void map2d(EncodeFn f, CUtensorMap* m, const void* p, uint64_t cols, uint64_t rows, uint32_t bc, uint32_t br,
           CUtensorMapSwizzle sw = CU_TENSOR_MAP_SWIZZLE_128B) {
  cuuint64_t dims[2] = {cols, rows};
  cuuint64_t strides[1] = {cols * 2};
  cuuint32_t box[2] = {bc, br}, es[2] = {1, 1};
  CUresult rc = f(m, CU_TENSOR_MAP_DATA_TYPE_BFLOAT16, 2, (void*)p, dims, strides, box, es, CU_TENSOR_MAP_INTERLEAVE_NONE,
    sw, CU_TENSOR_MAP_L2_PROMOTION_L2_128B, CU_TENSOR_MAP_FLOAT_OOB_FILL_NONE);
  if (rc != CUDA_SUCCESS) fprintf(stderr, "tensor map encode failed: %d\n", (int)rc);
}
void map_perm(EncodeFn f, CUtensorMap* m, const void* p, uint64_t rows) {
  cuuint64_t dims[5] = {64, 2, rows / 8, 4, DM / 64};
  cuuint64_t strides[4] = {DM * 2, 8 * DM * 2, 2 * DM * 2, 128};
  cuuint32_t box[5] = {64, 2, 4, 4, 2}, es[5] = {1, 1, 1, 1, 1};
  CUresult rc = f(m, CU_TENSOR_MAP_DATA_TYPE_BFLOAT16, 5, (void*)p, dims, strides, box, es, CU_TENSOR_MAP_INTERLEAVE_NONE,
    CU_TENSOR_MAP_SWIZZLE_128B, CU_TENSOR_MAP_L2_PROMOTION_L2_128B, CU_TENSOR_MAP_FLOAT_OOB_FILL_NONE);
  if (rc != CUDA_SUCCESS) fprintf(stderr, "tensor map encode failed: %d\n", (int)rc);
}

}

extern "C" void kernel_launch(void* const* d_in, const int* in_sizes, int n_in, void* d_out, int out_size) {
  void* fn = nullptr;
  cudaDriverEntryPointQueryResult qres;
  cudaGetDriverEntryPoint("cuTensorMapEncodeTiled", &fn, cudaEnableDefault, &qres);
  EncodeFn enc = (EncodeFn)fn;
  void *ph, *po, *pkv;
  cudaGetSymbolAddress(&ph, g_H);
  cudaGetSymbolAddress(&po, g_O);
  cudaGetSymbolAddress(&pkv, g_KV);
  Maps m;
  map2d(enc, &m.x, d_in[0], DM, SEQ, 64, 128);
  map2d(enc, &m.wq, d_in[1], DM, DM, 64, 32);
  map_perm(enc, &m.wo, d_in[4], DM);
  map2d(enc, &m.w1, d_in[6], FF, DM, 64, 32);
  map_perm(enc, &m.w2, d_in[7], FF);
  map2d(enc, &m.h, ph, FF, SEQ, 64, 128);
  map2d(enc, &m.o, po, DM, SEQ, 64, 128);
  map2d(enc, &m.kv, pkv, 32, 2 * SEQ, 32, 32, CU_TENSOR_MAP_SWIZZLE_64B);
  map2d(enc, &m.kvs, pkv, 32, 2 * SEQ, 8, 128, CU_TENSOR_MAP_SWIZZLE_NONE);
  Ptrs pt = {(const uint8_t*)d_in[2], (const uint8_t*)d_in[3]};
  cudaFuncSetAttribute(fused_kernel, cudaFuncAttributeMaxDynamicSharedMemorySize, SMEM_BYTES);
  fused_kernel<<<128, 384, SMEM_BYTES>>>(m, pt, (const __nv_bfloat16*)d_in[8], (uint8_t*)d_out);
}
```
